```python
import torch

def _softmax(x, axis=-1):
    return torch.softmax(x, dim=axis)
def _gelu(x):
    return torch.nn.functional.gelu(x, approximate="tanh")
def _silu(x):
    return torch.nn.functional.silu(x)
def _sigmoid(x):
    return torch.sigmoid(x)
def _layernorm(x, axis=-1, eps=1e-5):
    m = x.mean(dim=axis, keepdim=True)
    v = x.var(dim=axis, keepdim=True, unbiased=False)
    return (x - m) / torch.sqrt(v + eps)
def _scatter_add(tgt, idx, src, axis=0):
    return tgt.clone().index_add_(axis, idx, src)
def _segment_sum(src, seg, n):
    out = torch.zeros((n,) + src.shape[1:], dtype=src.dtype)
    return out.index_add_(0, seg, src)
def _pad(x, pw):
    flat = tuple(v for pair in reversed(pw) for v in pair)
    return torch.nn.functional.pad(x, flat)

kernel_name = 'sequential_preLN__gqa_block_cached__glu_gated_geglu__decode'

def setup_inputs():

    _w = (lambda a: (lambda t: t.to(torch.bfloat16) if t.is_floating_point() else t)(torch.as_tensor(a)))
    def _A_setup():
        B, Sq, D = 1, 1, 640
        Hq, Hkv, Sk, Dh = 32, 32, 4096, 128
        assert Hq % Hkv == 0, (Hq, Hkv)
        return {
            "x": _w((lambda *s: torch.randn(*s, dtype=torch.bfloat16) * 0.05)(B, Sq, D)),
            "k_cache": _w((lambda *s: torch.randn(*s, dtype=torch.bfloat16) * 1.6)(B, Hkv, Sk, Dh)),
            "v_cache": _w((lambda *s: torch.randn(*s, dtype=torch.bfloat16) * 0.8)(B, Hkv, Sk, Dh)),
            "wq": _w((lambda *s: torch.randn(*s, dtype=torch.bfloat16) * 1.6)(D, Hq * Dh) * (D ** -0.5)),
            "wo": _w((lambda *s: torch.randn(*s, dtype=torch.bfloat16) * 0.8)(Hq * Dh, D) * ((Hq * Dh) ** -0.5)),
        }
    _A_in = _A_setup()

    def _B_setup():
        B, S, Dm, Df = 1, 1, 640, 1728
        return {
            "x": _w((lambda *s: torch.randn(*s, dtype=torch.bfloat16) * 0.05)(B, S, Dm)),
            "w_gate": _w((lambda *s: torch.randn(*s, dtype=torch.bfloat16) * 0.4)(Dm, Df) * (Dm ** -0.5)),
            "w_up": _w((lambda *s: torch.randn(*s, dtype=torch.bfloat16) * 0.4)(Dm, Df) * (Dm ** -0.5)),
            "w_down": _w((lambda *s: torch.randn(*s, dtype=torch.bfloat16) * 0.4)(Df, Dm) * (Df ** -0.5)),
        }
    _B_in = _B_setup()

    return {
        "A_x": _A_in["x"],
        "A_k_cache": _A_in["k_cache"],
        "A_v_cache": _A_in["v_cache"],
        "A_wq": _A_in["wq"],
        "A_wo": _A_in["wo"],
        "B_x": _B_in["x"],
        "B_w_gate": _B_in["w_gate"],
        "B_w_up": _B_in["w_up"],
        "B_w_down": _B_in["w_down"],
    }

def reference(A_x, A_k_cache, A_v_cache, A_wq, A_wo, B_x, B_w_gate, B_w_up, B_w_down):
    def _A_ref(x, k_cache, v_cache, wq, wo):
        B, Sq, D = x.shape
        Hq, Dh = 32, 128
        Hkv = k_cache.shape[1]
        rep = Hq // Hkv
        q = (lambda x, *d: x.permute(*d))((x @ wq).reshape(B, Sq, Hq, Dh), 0, 2, 1, 3)
        k = (lambda x, n, axis: torch.repeat_interleave(x, n, dim=axis))(k_cache, rep, axis=1)
        v = (lambda x, n, axis: torch.repeat_interleave(x, n, dim=axis))(v_cache, rep, axis=1)
        scores = torch.einsum("bhqd,bhkd->bhqk", q, k) * (Dh ** -0.5)
        p = _softmax(scores, axis=-1)
        o = torch.einsum("bhqk,bhkd->bhqd", p, v)
        return (lambda x, *d: x.permute(*d))(o, 0, 2, 1, 3).reshape(B, Sq, Hq * Dh) @ wo

    def _B_ref(x, w_gate, w_up, w_down):
        g = torch.einsum("bsd,df->bsf", x, w_gate)
        u = torch.einsum("bsd,df->bsf", x, w_up)
        h = _gelu(g) * u
        return torch.einsum("bsf,fd->bsd", h, w_down)

    x = A_x
    h = x + _A_ref(_layernorm(x, axis=-1), A_k_cache, A_v_cache, A_wq, A_wo)
    h2 = h + _B_ref(_layernorm(h, axis=-1), B_w_gate, B_w_up, B_w_down)
    return h2
```

```cpp
#include <cuda_runtime.h>
#include <cuda.h>
#include <cuda_bf16.h>
#include <stdint.h>

namespace {

constexpr int D_MODEL = 640;
constexpr int NH = 32;
constexpr int SK = 4096;
constexpr int DH = 128;
constexpr int DFF = 1728;
constexpr int NCTA = NH * 4;
constexpr int KEYS_PER_CTA = SK / 4;
constexpr int CHUNK_KEYS = 64;
constexpr int CHUNK_BYTES = CHUNK_KEYS * DH * 2;
constexpr int NCH = KEYS_PER_CTA / CHUNK_KEYS;
constexpr int NSLOT = 13;
constexpr int NTHREADS = 352;
constexpr int NTAIL = 320;
constexpr int NFFN = DFF / 16;
constexpr unsigned SPIN_LIMIT = 1u << 22;

constexpr int DMIN = 2;
constexpr int DMAX = 4;
constexpr int PACE_NS = 660;
constexpr int LEAD_NS = 700;
constexpr int DL_WO = 4, DL_GU = 3, DL_GU2 = 6, DL_DN = 2;
constexpr int PBN = 6;
constexpr int HREP = 2;
constexpr int LSTRIDE = 72;
struct __align__(128) Scratch {
    float4 o_acc[NH * 8 * LSTRIDE];
    float4 h_acc[HREP][40 * LSTRIDE];
    float4 out_acc[40 * LSTRIDE];
    uint2 qx[NH][64];
    float4 ml[NH][32][2];
    unsigned zero_tag[8];
    unsigned inbox_tag[NCTA][8];
};
__device__ Scratch g_s;
__device__ unsigned g_epoch = 1;
__device__ __forceinline__ int pk_idx(int pk) { return (pk >> 3) * LSTRIDE + (pk & 7); }

__device__ __forceinline__ void mbar_init(uint32_t bar, uint32_t cnt) {
    asm volatile("mbarrier.init.shared::cta.b64 [%0], %1;" :: "r"(bar), "r"(cnt) : "memory");
}
__device__ __forceinline__ void mbar_expect_tx(uint32_t bar, uint32_t bytes) {
    asm volatile("mbarrier.arrive.expect_tx.shared::cta.b64 _, [%0], %1;" :: "r"(bar), "r"(bytes) : "memory");
}
__device__ __forceinline__ void mbar_arrive(uint32_t bar) {
    asm volatile("mbarrier.arrive.shared::cta.b64 _, [%0];" :: "r"(bar) : "memory");
}
__device__ __forceinline__ bool mbar_try(uint32_t bar, uint32_t parity) {
    uint32_t ok;
    asm volatile("{\n.reg .pred p;\nmbarrier.try_wait.parity.shared::cta.b64 p, [%1], %2;\nselp.u32 %0, 1, 0, p;\n}"
                 : "=r"(ok) : "r"(bar), "r"(parity) : "memory");
    return ok != 0;
}
__device__ __forceinline__ bool mbar_test(uint32_t bar, uint32_t parity) {
    uint32_t ok;
    asm volatile("{\n.reg .pred p;\nmbarrier.test_wait.parity.shared::cta.b64 p, [%1], %2;\nselp.u32 %0, 1, 0, p;\n}"
                 : "=r"(ok) : "r"(bar), "r"(parity) : "memory");
    return ok != 0;
}
__device__ __forceinline__ void mbar_wait(uint32_t bar, uint32_t parity) {
    unsigned it = 0;
    while (!mbar_try(bar, parity)) { if (++it > SPIN_LIMIT) __trap(); }
}
__device__ __forceinline__ uint32_t gtime32() {
    uint32_t t;
    asm volatile("mov.u32 %0, %%globaltimer_lo;" : "=r"(t) :: "memory");
    return t;
}
__device__ __forceinline__ void bulk_load(uint32_t dst, const void* src, uint32_t bytes, uint32_t bar, uint64_t pol) {
    asm volatile("cp.async.bulk.shared::cluster.global.mbarrier::complete_tx::bytes.L2::cache_hint [%0], [%1], %2, [%3], %4;"
                 :: "r"(dst), "l"(src), "r"(bytes), "r"(bar), "l"(pol) : "memory");
}
__device__ __forceinline__ void tensor_load(uint32_t dst, const CUtensorMap* map, int c0, int c1, uint32_t bar) {
    asm volatile("cp.async.bulk.tensor.2d.shared::cluster.global.mbarrier::complete_tx::bytes [%0], [%1, {%2, %3}], [%4];"
                 :: "r"(dst), "l"(map), "r"(c0), "r"(c1), "r"(bar) : "memory");
}
__device__ __forceinline__ uint4 lds128(uint32_t addr) {
    uint4 v;
    asm volatile("ld.shared.v4.u32 {%0,%1,%2,%3}, [%4];" : "=r"(v.x), "=r"(v.y), "=r"(v.z), "=r"(v.w) : "r"(addr) : "memory");
    return v;
}
__device__ __forceinline__ float4 lds128f(uint32_t addr) {
    float4 v;
    asm volatile("ld.volatile.shared.v4.f32 {%0,%1,%2,%3}, [%4];" : "=f"(v.x), "=f"(v.y), "=f"(v.z), "=f"(v.w) : "r"(addr) : "memory");
    return v;
}
__device__ __forceinline__ float2 lds64f(uint32_t addr) {
    float2 v;
    asm volatile("ld.shared.v2.f32 {%0,%1}, [%2];" : "=f"(v.x), "=f"(v.y) : "r"(addr) : "memory");
    return v;
}
__device__ __forceinline__ uint32_t lds32(uint32_t addr) {
    uint32_t v;
    asm volatile("ld.volatile.shared.u32 %0, [%1];" : "=r"(v) : "r"(addr) : "memory");
    return v;
}
__device__ __forceinline__ void sts32(uint32_t addr, uint32_t v) {
    asm volatile("st.volatile.shared.u32 [%0], %1;" :: "r"(addr), "r"(v) : "memory");
}
__device__ __forceinline__ void stsf(uint32_t addr, float v) { sts32(addr, __float_as_uint(v)); }
__device__ __forceinline__ float ldsf(uint32_t addr) { return __uint_as_float(lds32(addr)); }
__device__ __forceinline__ void cp_async16(uint32_t dst, const void* src) {
    asm volatile("cp.async.cg.shared.global [%0], [%1], 16;" :: "r"(dst), "l"(src) : "memory");
}
__device__ __forceinline__ void poll_async(uint32_t dst, const float4* src) {
    stsf(dst + 8, -1.0f);
    cp_async16(dst, src);
}
__device__ __forceinline__ float4 ld_poll(const float4* p) {
    float4 v;
    asm volatile("ld.relaxed.gpu.global.v4.f32 {%0,%1,%2,%3}, [%4];"
                 : "=f"(v.x), "=f"(v.y), "=f"(v.z), "=f"(v.w) : "l"(p) : "memory");
    return v;
}
__device__ __forceinline__ unsigned ld_u32_relaxed(const unsigned* p) {
    unsigned v;
    asm volatile("ld.relaxed.gpu.global.u32 %0, [%1];" : "=r"(v) : "l"(p) : "memory");
    return v;
}
__device__ __forceinline__ void red_pkt(float4* p, float a, float b) {
    asm volatile("red.relaxed.gpu.global.add.v4.f32 [%0], {%1,%2,%3,%4};"
                 :: "l"(p), "f"(a), "f"(b), "f"(1.0f), "f"(0.0f) : "memory");
}
__device__ __forceinline__ void ldsm4(uint32_t& r0, uint32_t& r1, uint32_t& r2, uint32_t& r3, uint32_t addr) {
    asm volatile("ldmatrix.sync.aligned.m8n8.x4.shared.b16 {%0,%1,%2,%3}, [%4];"
                 : "=r"(r0), "=r"(r1), "=r"(r2), "=r"(r3) : "r"(addr) : "memory");
}
__device__ __forceinline__ void ldsm4t(uint32_t& r0, uint32_t& r1, uint32_t& r2, uint32_t& r3, uint32_t addr) {
    asm volatile("ldmatrix.sync.aligned.m8n8.x4.trans.shared.b16 {%0,%1,%2,%3}, [%4];"
                 : "=r"(r0), "=r"(r1), "=r"(r2), "=r"(r3) : "r"(addr) : "memory");
}
__device__ __forceinline__ void mma16816(float (&c)[4], uint32_t a0, uint32_t a1, uint32_t a2, uint32_t a3,
                                         uint32_t b0, uint32_t b1) {
    asm volatile("mma.sync.aligned.m16n8k16.row.col.f32.bf16.bf16.f32 {%0,%1,%2,%3}, {%4,%5,%6,%7}, {%8,%9}, {%0,%1,%2,%3};"
                 : "+f"(c[0]), "+f"(c[1]), "+f"(c[2]), "+f"(c[3])
                 : "r"(a0), "r"(a1), "r"(a2), "r"(a3), "r"(b0), "r"(b1));
}
__device__ __forceinline__ uint32_t pack_bf16(float lo, float hi) {
    uint32_t r;
    asm("cvt.rn.bf16x2.f32 %0, %1, %2;" : "=r"(r) : "f"(hi), "f"(lo));
    return r;
}
__device__ __forceinline__ float bf16r(float x) { return __uint_as_float(pack_bf16(0.f, x)); }
__device__ __forceinline__ float bf_lo(uint32_t w) { return __uint_as_float(w << 16); }
__device__ __forceinline__ float bf_hi(uint32_t w) { return __uint_as_float(w & 0xffff0000u); }
__device__ __forceinline__ void gemv_mma(float (&c)[4], const uint4& w, uint32_t pair, uint32_t sel0, uint32_t sel1) {
    mma16816(c, w.x, w.y, w.z, w.w, __byte_perm(pair, 0u, sel0), __byte_perm(pair, 0u, sel1));
}
__device__ __forceinline__ void make_sel(int g, int half, uint32_t& sel0, uint32_t& sel1) {
    const uint32_t src = half ? 0x32u : 0x10u;
    const uint32_t x = (g & 1) ? ((src << 8) | 0x44u) : (0x4400u | src);
    sel0 = (g & 2) ? 0x4444u : x;
    sel1 = (g & 2) ? x : 0x4444u;
}
__device__ __forceinline__ float ex2(float x) { float y; asm("ex2.approx.ftz.f32 %0, %1;" : "=f"(y) : "f"(x)); return y; }
__device__ __forceinline__ float rcp(float x) { float y; asm("rcp.approx.ftz.f32 %0, %1;" : "=f"(y) : "f"(x)); return y; }
__device__ __forceinline__ float sqrt_fast(float x) { float y; asm("sqrt.approx.ftz.f32 %0, %1;" : "=f"(y) : "f"(x)); return y; }
__device__ __forceinline__ void named_bar(int id, int cnt) { asm volatile("bar.sync %0, %1;" :: "r"(id), "r"(cnt) : "memory"); }
__device__ __forceinline__ void fence_gpu() { asm volatile("fence.acq_rel.gpu;" ::: "memory"); }
template <typename T> __device__ __forceinline__ void pin32(T& v) { asm volatile("" : "+r"(v)); }
template <typename T> __device__ __forceinline__ void pin64(T& v) { asm volatile("" : "+l"(v)); }

constexpr float LOG2E = 1.4426950408889634f;
constexpr int WPITCH = D_MODEL * 2 + 32;
constexpr int LATE_SLOT = 2 * NCH - 2 * NSLOT;
constexpr int OFF_WQ = (NSLOT - 3) * CHUNK_BYTES;
constexpr int OFF_WO = LATE_SLOT * CHUNK_BYTES;
constexpr int OFF_GU = OFF_WO + 40960;
constexpr int OFF_WD = OFF_GU + 40960;
constexpr int WD_LAST = (OFF_WD + 16 * WPITCH - 1) / CHUNK_BYTES;
static_assert(3 * NSLOT >= 2 * NCH && LATE_SLOT >= 1 && WD_LAST < NSLOT && OFF_GU % 128 == 0, "overlay layout");
constexpr int OFF_HB = 0;
constexpr int OFF_BAR = NSLOT * CHUNK_BYTES;
constexpr int OFF_X = OFF_BAR + 384;
constexpr int OFF_PART = OFF_X + 1280;
constexpr int OFF_CS = OFF_PART + 2560;
constexpr int OFF_STAT = OFF_CS + 1536;
constexpr int OFF_SC = OFF_STAT + 128;
constexpr int OFF_P = OFF_SC + 4096;
constexpr int OFF_OB = OFF_P + 2048;
constexpr int OFF_OF = OFF_OB + 3072;
constexpr int OFF_QB = OFF_OF + 256;
constexpr int SMEM_BYTES = OFF_QB + 1536;
static_assert(SMEM_BYTES <= 232448, "shared memory budget");
static_assert(2 * NSLOT + 18 <= 48 && DMAX <= PBN && DMAX >= 3 && DMIN >= 1 && DMIN <= DMAX && DMAX < NSLOT, "barriers / pacing");

__global__ void __launch_bounds__(NTHREADS, 1)
fused_decode_kernel(const __grid_constant__ CUtensorMap map_wq, const __grid_constant__ CUtensorMap map_wg,
                    const __grid_constant__ CUtensorMap map_wu, const __grid_constant__ CUtensorMap map_wo,
                    const __nv_bfloat16* __restrict__ x, const __nv_bfloat16* __restrict__ kc,
                    const __nv_bfloat16* __restrict__ vc,
                    const __nv_bfloat16* __restrict__ wd, __nv_bfloat16* __restrict__ out) {
    extern __shared__ __align__(1024) unsigned char smem[];
    uint32_t sb = (uint32_t)__cvta_generic_to_shared(smem);
    const int tid = threadIdx.x, warp = tid >> 5, lane = tid & 31;
    const int bid = blockIdx.x, h = bid >> 2, s = bid & 3;
    const size_t kvoff = (size_t)bid * (KEYS_PER_CTA * DH * 2);
    const unsigned char* kbase = reinterpret_cast<const unsigned char*>(kc) + kvoff;
#define BAR_FULL (sb + OFF_BAR)
#define BAR_EMPTY (sb + OFF_BAR + 8 * NSLOT)
#define BAR_X (sb + OFF_BAR + 16 * NSLOT)
#define BAR_WQ (BAR_X + 8)
#define BAR_WO (BAR_X + 16)
#define BAR_GU (BAR_X + 48)
#define BAR_DN (BAR_X + 80)
#define BAR_WQFREE (BAR_X + 96)
#define BAR_OK (BAR_X + 104)
#define BAR_KDONE (BAR_X + 112)
#define BAR_VDONE (BAR_X + 120)
#define BAR_O (BAR_X + 128)
#define BAR_NONE (BAR_X + 136)

    const uint32_t t_start = gtime32();
    uint64_t pol;
    asm volatile("createpolicy.fractional.L2::evict_first.b64 %0, 1.0;" : "=l"(pol));
    if (tid == 320) {
        mbar_init(BAR_X, 1); mbar_init(BAR_WQ, 1);
        asm volatile("fence.mbarrier_init.release.cluster;" ::: "memory");
        mbar_expect_tx(BAR_X, 1280);
        bulk_load(sb + OFF_X, x, 1280, BAR_X, pol);
        mbar_expect_tx(BAR_WQ, 40960);
        #pragma unroll
        for (int i = 0; i < 4; i++) tensor_load(sb + OFF_WQ + 10240 * i, &map_wq, 32 * bid, 160 * i, BAR_WQ);
    } else if (tid == 288) {
        mbar_init(BAR_FULL, 1); mbar_init(BAR_FULL + 8, 1);
        asm volatile("fence.mbarrier_init.release.cluster;" ::: "memory");
        #pragma unroll
        for (int i = 0; i < 2; i++) {
            mbar_expect_tx(BAR_FULL + 8 * i, CHUNK_BYTES);
            bulk_load(sb + i * CHUNK_BYTES, kbase + i * CHUNK_BYTES, CHUNK_BYTES, BAR_FULL + 8 * i, pol);
        }
        #pragma unroll
        for (int i = 2; i < NSLOT; i++) mbar_init(BAR_FULL + 8 * i, 1);
        #pragma unroll
        for (int i = 0; i < NSLOT; i++) mbar_init(BAR_EMPTY + 8 * i, 4);
        #pragma unroll
        for (int i = 0; i < 10; i++) mbar_init(BAR_WO + 8 * i, 1);
        mbar_init(BAR_WQFREE, 8); mbar_init(BAR_OK, 1); mbar_init(BAR_KDONE, 8); mbar_init(BAR_VDONE, 8); mbar_init(BAR_O, 1); mbar_init(BAR_NONE, 1);
        asm volatile("fence.mbarrier_init.release.cluster;" ::: "memory");
    } else if (warp == 8) {
        #pragma unroll
        for (int j = 0; j < 6; j++) sts32(sb + OFF_OB + 512 * j + 16 * lane + 8, 0u);
        #pragma unroll
        for (int j = 0; j < 3; j++) { sts32(sb + OFF_QB + 512 * j + 16 * lane + 4, 0u); sts32(sb + OFF_QB + 512 * j + 16 * lane + 12, 0u); }
    }
    const unsigned tag = ld_u32_relaxed(&g_epoch);
    __syncthreads();

    if (warp == 10) {
        uint32_t pb[PBN];
        #pragma unroll
        for (int i = 0; i < PBN; i++) pb[i] = BAR_NONE | 1u;
        pb[PBN - 2] = BAR_FULL; pb[PBN - 1] = BAR_FULL + 8;
        uint32_t due = t_start + (2 * CHUNK_BYTES + 40960) / 64 * PACE_NS / 256 - LEAD_NS;
        auto pace = [&](uint32_t bar, uint32_t par, uint32_t bytes, uint32_t step) {
            mbar_wait(pb[PBN - DMAX] & ~1u, pb[PBN - DMAX] & 1u);
            unsigned it = 0;
            const uint32_t pm = pb[PBN - DMIN];
            while (!mbar_test(pm & ~1u, pm & 1u) && (int)(gtime32() - due) < 0) {
                if (++it > SPIN_LIMIT) __trap();
            }
            due += step;
            #pragma unroll
            for (int i = 0; i + 1 < PBN; i++) pb[i] = pb[i + 1];
            pb[PBN - 1] = bar | par;
            if (lane == 0) mbar_expect_tx(bar, bytes);
            __syncwarp();
        };
        const unsigned char* vbase = reinterpret_cast<const unsigned char*>(vc) + kvoff;
        int slot = 2, uses = 0;
        #pragma unroll 1
        for (int i = 2; i < 2 * NCH; i++) {
            if (i == NSLOT - 3) mbar_wait(BAR_WQFREE, 0);
            if (uses > 0) mbar_wait(BAR_EMPTY + 8 * slot, (uses - 1) & 1);
            pace(BAR_FULL + 8 * slot, uses & 1, CHUNK_BYTES, PACE_NS);
            const unsigned char* src = ((i < NCH) ? kbase : vbase) + (i & (NCH - 1)) * CHUNK_BYTES;
            if (lane == 0) bulk_load(sb + slot * CHUNK_BYTES, src, CHUNK_BYTES, BAR_FULL + 8 * slot, pol);
            if (++slot == NSLOT) { slot = 0; uses++; }
        }
        #pragma unroll 1
        for (int k = LATE_SLOT; k <= WD_LAST; k++) mbar_wait(BAR_EMPTY + 8 * k, 1);
        auto pace_late = [&](uint32_t bar, uint32_t old) {
            mbar_wait(old & ~1u, old & 1u);
            #pragma unroll
            for (int i = 0; i + 1 < PBN; i++) pb[i] = pb[i + 1];
            pb[PBN - 1] = bar;
            if (lane == 0) mbar_expect_tx(bar, 10240);
            __syncwarp();
        };
        #pragma unroll 1
        for (int j = 0; j < 4; j++) {
            pace_late(BAR_WO + 8 * j, pb[PBN - DL_WO]);
            if (lane == 0)
                tensor_load(sb + OFF_WO + (j & 1) * 20480 + (j >> 1) * 10240, &map_wo, 160 * s + 80 * (j & 1), h * DH + 64 * (j >> 1), BAR_WO + 8 * j);
        }
        if (bid < NFFN) {
            #pragma unroll 1
            for (int j = 0; j < 4; j++) {
                pace_late(BAR_GU + 8 * j, j < 2 ? pb[PBN - DL_GU] : pb[PBN - DL_GU2]);
                if (lane < 2) tensor_load(sb + OFF_GU + 20480 * lane + 5120 * j, lane ? &map_wu : &map_wg, 16 * bid, 160 * j, BAR_GU + 8 * j);
            }
            #pragma unroll 1
            for (int j = 0; j < 2; j++) {
                pace_late(BAR_DN + 8 * j, pb[PBN - DL_DN]);
                if (lane < 8)
                    bulk_load(sb + OFF_WD + (8 * j + lane) * WPITCH, wd + (size_t)(16 * bid + 8 * j + lane) * D_MODEL, D_MODEL * 2, BAR_DN + 8 * j, pol);
            }
        }
    }

    pin32(sb);
    const int g = lane >> 2, z = lane & 3;
    uint32_t selL0, selL1, selH0, selH1;
    make_sel(g, 0, selL0, selL1);
    make_sel(g, 1, selH0, selH1);
    uint4 wr[8];
    float acc[8][4];
    float fw = 0.f;

    int pass;
    asm volatile("mov.u32 %0, %1;" : "=r"(pass) : "r"((warp == 9) ? 0 : (warp == 10 ? 2 : 1)));
    #pragma unroll 1
    for (; pass < 2; pass++) {
    const bool real = (pass == 1);
    if (real) {
    if (warp < 8) {
        if (lane < 2)
            asm volatile("st.relaxed.gpu.global.v4.f32 [%0], {%1,%1,%1,%1};" :: "l"(&g_s.ml[h][s * 8 + warp][lane]), "f"(0.f) : "memory");
        mbar_wait(BAR_X, 0);
        uint4 xv[3];
        xv[0] = lds128(sb + OFF_X + 16 * lane); xv[1] = lds128(sb + OFF_X + 512 + 16 * lane);
        xv[2] = (lane < 16) ? lds128(sb + OFF_X + 1024 + 16 * lane) : make_uint4(0, 0, 0, 0);
        float sum = 0.f;
        #pragma unroll
        for (int i = 0; i < 3; i++) {
            const uint32_t w4[4] = {xv[i].x, xv[i].y, xv[i].z, xv[i].w};
            #pragma unroll
            for (int k = 0; k < 4; k++) sum += bf_lo(w4[k]) + bf_hi(w4[k]);
        }
        #pragma unroll
        for (int o = 16; o > 0; o >>= 1) sum += __shfl_xor_sync(0xffffffffu, sum, o);
        const float mean = sum * (1.0f / D_MODEL);
        float sq = 0.f;
        #pragma unroll
        for (int i = 0; i < 3; i++) {
            if (i < 2 || lane < 16) {
                const uint32_t w4[4] = {xv[i].x, xv[i].y, xv[i].z, xv[i].w};
                #pragma unroll
                for (int k = 0; k < 4; k++) {
                    float a = bf_lo(w4[k]) - mean, b = bf_hi(w4[k]) - mean;
                    sq += a * a + b * b;
                }
            }
        }
        #pragma unroll
        for (int o = 16; o > 0; o >>= 1) sq += __shfl_xor_sync(0xffffffffu, sq, o);
        const float mean_b = bf16r(mean);
        const float den = bf16r(sqrtf(bf16r(bf16r(sq * (1.0f / D_MODEL)) + 1e-5f)));
        {
            const int row0 = 80 * warp + 4 * (lane >> 4) + z;
            const unsigned short* xs = reinterpret_cast<const unsigned short*>(smem + OFF_X) + row0;
            uint32_t xn[10];
            #pragma unroll
            for (int t = 0; t < 10; t++) xn[t] = pack_bf16(__fdiv_rn(bf16r(bf_lo(xs[8 * t]) - mean_b), den), 0.f);
            mbar_wait(BAR_WQ, 0);
            const uint32_t wa = sb + OFF_WQ + row0 * 64 + (g & 3) * 16;
            float qa[2][4] = {};
            #pragma unroll
            for (int t = 0; t < 10; t++) gemv_mma(qa[t & 1], lds128(wa + t * 512), xn[t], selL0, selL1);
            if ((z >> 1) == (lane >> 4)) {
                #pragma unroll
                for (int k = 0; k < 4; k++)
                    stsf(sb + OFF_PART + 4 * (((g & 3) * 8 + (z & 1) * 4 + k) * 20 + 2 * warp + (lane >> 4)), qa[0][k] + qa[1][k]);
            }
        }
        asm volatile("bar.arrive 5, 288;" ::: "memory");
        if (lane == 0) mbar_arrive(BAR_WQFREE);
        uint32_t qf[8][2];
        {
            uint32_t qsel = 0;
            unsigned it = 0;
            while (true) {
                bool done = false;
                #pragma unroll
                for (int j = 0; j < 3; j++) {
                    const uint32_t ta = lds32(sb + OFF_QB + 512 * j + 16 * lane + 4), tb = lds32(sb + OFF_QB + 512 * j + 16 * lane + 12);
                    if (__all_sync(0xffffffffu, ta == tag && tb == tag)) { qsel = 512 * j; done = true; break; }
                }
                if (done) break;
                if (++it > SPIN_LIMIT) __trap();
                __nanosleep(100);
            }
            #pragma unroll
            for (int c = 0; c < 8; c++) {
                const uint32_t a = sb + OFF_QB + qsel + 8 * (((c + g) & 7) * 4 + z);
                qf[c][0] = lds32(a);
                qf[c][1] = lds32(a + 256);
            }
        }

        const int r8 = lane & 7;
        const bool diag = (z == (g >> 1));
        const uint32_t koff = sb + (warp & 3) * 4096 + (r8 + 8 * ((lane >> 3) & 1)) * 256 + (lane >> 4) * 128;
        const uint32_t voff = sb + (warp & 3) * 4096 + (r8 + 8 * (lane >> 4)) * 256 + ((lane >> 3) & 1) * 128;
        int slot = warp >> 2, phase = 0;
        float* scw = reinterpret_cast<float*>(smem + OFF_SC) + warp * 128;
        #pragma unroll 1
        for (int i = 0; i < 8; i++) {
            mbar_wait(BAR_FULL + 8 * slot, phase);
            const uint32_t base = koff + slot * CHUNK_BYTES;
            float c0[4] = {}, c1[4] = {};
            #pragma unroll
            for (int c = 0; c < 8; c += 2) {
                uint32_t a0, a1, a2, a3, b0, b1, b2, b3;
                ldsm4(a0, a1, a2, a3, base + (((c + r8) & 7) << 4));
                ldsm4(b0, b1, b2, b3, base + (((c + 1 + r8) & 7) << 4));
                mma16816(c0, a0, a1, a2, a3, qf[c][0], qf[c][1]);
                mma16816(c1, b0, b1, b2, b3, qf[c + 1][0], qf[c + 1][1]);
            }
            __syncwarp();
            if (lane == 0) mbar_arrive(BAR_EMPTY + 8 * slot);
            if (diag) {
                const float da = (g & 1) ? (c0[1] + c1[1]) : (c0[0] + c1[0]);
                const float db = (g & 1) ? (c0[3] + c1[3]) : (c0[2] + c1[2]);
                scw[16 * i + g] = bf16r(bf16r(da) * 0.08838834764831845f);
                scw[16 * i + 8 + g] = bf16r(bf16r(db) * 0.08838834764831845f);
            }
            slot += 2;
            if (slot >= NSLOT) { slot -= NSLOT; phase ^= 1; }
        }
        __syncwarp();
        const float4 s4 = *reinterpret_cast<const float4*>(scw + 4 * lane);
        float m = fmaxf(fmaxf(s4.x, s4.y), fmaxf(s4.z, s4.w));
        #pragma unroll
        for (int o = 16; o > 0; o >>= 1) m = fmaxf(m, __shfl_xor_sync(0xffffffffu, m, o));
        const float mneg = -m * LOG2E;
        const float p0 = ex2(fmaf(s4.x, LOG2E, mneg)), p1 = ex2(fmaf(s4.y, LOG2E, mneg));
        const float p2 = ex2(fmaf(s4.z, LOG2E, mneg)), p3 = ex2(fmaf(s4.w, LOG2E, mneg));
        float l = (p0 + p1) + (p2 + p3);
        unsigned short* pw = reinterpret_cast<unsigned short*>(smem + OFF_P) + warp * 128;
        *reinterpret_cast<uint2*>(pw + 4 * lane) = make_uint2(pack_bf16(p0, p1), pack_bf16(p2, p3));
        #pragma unroll
        for (int o = 16; o > 0; o >>= 1) l += __shfl_xor_sync(0xffffffffu, l, o);
        if (lane < 2)
            asm volatile("st.relaxed.gpu.global.v4.f32 [%0], {%1,%2,%3,%4};"
                         :: "l"(&g_s.ml[h][s * 8 + warp][lane]), "f"(m), "f"(l), "f"(__uint_as_float(tag)), "f"(0.f) : "memory");
        if (lane == 0) mbar_arrive(BAR_KDONE);
        __syncwarp();

        const int psh = (g & 1) * 16;
        #pragma unroll
        for (int c = 0; c < 8; c++) { acc[c][0] = 0.f; acc[c][1] = 0.f; acc[c][2] = 0.f; acc[c][3] = 0.f; }
        #pragma unroll 1
        for (int i = 0; i < 8; i++) {
            uint32_t pa = 0, pb = 0;
            if (diag) { pa = (uint32_t)pw[16 * i + g] << psh; pb = (uint32_t)pw[16 * i + 8 + g] << psh; }
            if (i == 7) {
                mbar_wait(BAR_OK, 0);
                fw = ex2((m - ldsf(sb + OFF_STAT + 80)) * LOG2E) * ldsf(sb + OFF_STAT + 84);
            }
            mbar_wait(BAR_FULL + 8 * slot, phase);
            const uint32_t base = voff + slot * CHUNK_BYTES;
            #pragma unroll
            for (int c = 0; c < 8; c++) {
                uint32_t a0, a1, a2, a3;
                ldsm4t(a0, a1, a2, a3, base + (((c + r8) & 7) << 4));
                mma16816(acc[c], a0, a1, a2, a3, pa, pb);
            }
            __syncwarp();
            if (lane == 0) mbar_arrive(BAR_EMPTY + 8 * slot);
            slot += 2;
            if (slot >= NSLOT) { slot -= NSLOT; phase ^= 1; }
        }
    } else {
        #pragma unroll
        for (int c = 0; c < 8; c++) { acc[c][0] = 0.f; acc[c][1] = 0.f; acc[c][2] = 0.f; acc[c][3] = 0.f; }
        if (warp == 8) {
            if ((lane & 1) == 0)
                asm volatile("st.relaxed.gpu.global.v2.u32 [%0], {%1,%1};" :: "l"(&g_s.qx[h][16 * s + (lane >> 1)]), "r"(0u) : "memory");
            named_bar(5, 288);
            float qv = 0.f;
            #pragma unroll
            for (int k = 0; k < 4; k++) { const float4 v = lds128f(sb + OFF_PART + 80 * lane + 16 * k); qv += (v.x + v.y) + (v.z + v.w); }
            const float nx = __shfl_down_sync(0xffffffffu, qv, 1);
            if ((lane & 1) == 0)
                asm volatile("st.relaxed.gpu.global.v2.u32 [%0], {%1,%2};"
                             :: "l"(&g_s.qx[h][16 * s + (lane >> 1)]), "r"(pack_bf16(qv, nx)), "r"(tag) : "memory");
            unsigned it = 0;
            while (true) {
                bool done = false;
                #pragma unroll
                for (int j = 0; j < 3; j++) {
                    const uint32_t a = sb + OFF_QB + 512 * j + 16 * lane;
                    const uint32_t ta = lds32(a + 4), tb = lds32(a + 12);
                    if (__all_sync(0xffffffffu, ta == tag && tb == tag)) { done = true; break; }
                    if (__all_sync(0xffffffffu, tb != 0xffffffffu)) {
                        sts32(a + 12, 0xffffffffu);
                        cp_async16(a, &g_s.qx[h][2 * lane]);
                        __nanosleep(150);
                    }
                }
                if (done) break;
                if (++it > 16u * SPIN_LIMIT) __trap();
            }
            mbar_wait(BAR_OK, 0);
        } else {
            if (lane == 0) {
                asm volatile("prefetch.tensormap [%0];" :: "l"(&map_wo) : "memory");
                asm volatile("prefetch.tensormap [%0];" :: "l"(&map_wg) : "memory");
                asm volatile("prefetch.tensormap [%0];" :: "l"(&map_wu) : "memory");
            }
            if (lane < 16) g_s.o_acc[pk_idx(64 * h + 16 * s + lane)] = make_float4(0.f, 0.f, 0.f, 0.f);
            if (bid == 0) {
                #pragma unroll 1
                for (int i = 0; i < 10; i++) {
                    #pragma unroll
                    for (int r = 0; r < HREP; r++) g_s.h_acc[r][pk_idx(32 * i + lane)] = make_float4(0.f, 0.f, 0.f, 0.f);
                    g_s.out_acc[pk_idx(32 * i + lane)] = make_float4(0.f, 0.f, 0.f, 0.f);
                }
            }
            __syncwarp();
            fence_gpu();
            if (lane < 8) {
                asm volatile("st.relaxed.gpu.global.u32 [%0], %1;" :: "l"(&g_s.inbox_tag[bid][lane]), "r"(tag) : "memory");
                if (bid == 0) asm volatile("st.relaxed.gpu.global.u32 [%0], %1;" :: "l"(&g_s.zero_tag[lane]), "r"(tag) : "memory");
            }
            mbar_wait(BAR_KDONE, 0);
            const unsigned* tp = (lane < 4) ? &g_s.inbox_tag[4 * h + lane][0] : &g_s.zero_tag[0];
            unsigned it = 0;
            float4 e;
            while (true) {
                e = ld_poll(&g_s.ml[h][lane][0]);
                const unsigned tv = ld_u32_relaxed(tp);
                if (__all_sync(0xffffffffu, __float_as_uint(e.z) == tag && tv == tag)) break;
                if (++it > SPIN_LIMIT) __trap();
                __nanosleep(300);
            }
            fence_gpu();
            float mh = e.x;
            #pragma unroll
            for (int o = 16; o > 0; o >>= 1) mh = fmaxf(mh, __shfl_xor_sync(0xffffffffu, mh, o));
            float lh = e.y * ex2((e.x - mh) * LOG2E);
            #pragma unroll
            for (int o = 16; o > 0; o >>= 1) lh += __shfl_xor_sync(0xffffffffu, lh, o);
            if (lane == 0) {
                stsf(sb + OFF_STAT + 80, mh); stsf(sb + OFF_STAT + 84, __fdividef(1.0f, lh));
                mbar_arrive(BAR_OK);
            }
            __syncwarp();
        }
        mbar_wait(BAR_X, 0);
        if (warp == 8) mbar_wait(BAR_VDONE, 0);
    }
    }

    if (warp < 8 || !real) {
        float t[8], u[8];
        #pragma unroll
        for (int c = 0; c < 8; c++) { t[c] = acc[c][0] + acc[(c + 7) & 7][1]; u[c] = acc[c][2] + acc[(c + 7) & 7][3]; }
        const int l1 = (lane & ~3) | ((z + 1) & 3), l2 = lane ^ 2, l3 = (lane & ~3) | ((z + 3) & 3);
        const float a0 = (t[0] + __shfl_sync(0xffffffffu, t[6], l1)) + (__shfl_sync(0xffffffffu, t[4], l2) + __shfl_sync(0xffffffffu, t[2], l3));
        const float a1 = (t[1] + __shfl_sync(0xffffffffu, t[7], l1)) + (__shfl_sync(0xffffffffu, t[5], l2) + __shfl_sync(0xffffffffu, t[3], l3));
        const float b0 = (u[0] + __shfl_sync(0xffffffffu, u[6], l1)) + (__shfl_sync(0xffffffffu, u[4], l2) + __shfl_sync(0xffffffffu, u[2], l3));
        const float b1 = (u[1] + __shfl_sync(0xffffffffu, u[7], l1)) + (__shfl_sync(0xffffffffu, u[5], l2) + __shfl_sync(0xffffffffu, u[3], l3));
        if (real) {
            asm volatile("st.shared.v4.f32 [%0], {%1,%2,%3,%4};"
                         :: "r"(sb + OFF_SC + 512 * warp + 16 * lane), "f"(a0 * fw), "f"(a1 * fw), "f"(b0 * fw), "f"(b1 * fw) : "memory");
            __syncwarp();
            if (lane == 0) mbar_arrive(BAR_VDONE);
        }
    }
    if (warp == 9) {
        float4* oacc = g_s.o_acc + (8 * h + z) * LSTRIDE + g;
        pin64(oacc);
        if (real) mbar_wait(BAR_VDONE, 0);
        float4 v[8];
        #pragma unroll
        for (int k = 0; k < 8; k++) v[k] = lds128f(sb + OFF_SC + 512 * k + 16 * lane);
        const float a0 = ((v[0].x + v[1].x) + (v[2].x + v[3].x)) + ((v[4].x + v[5].x) + (v[6].x + v[7].x));
        const float a1 = ((v[0].y + v[1].y) + (v[2].y + v[3].y)) + ((v[4].y + v[5].y) + (v[6].y + v[7].y));
        const float b0 = ((v[0].z + v[1].z) + (v[2].z + v[3].z)) + ((v[4].z + v[5].z) + (v[6].z + v[7].z));
        const float b1 = ((v[0].w + v[1].w) + (v[2].w + v[3].w)) + ((v[4].w + v[5].w) + (v[6].w + v[7].w));
        if (real) { red_pkt(oacc, a0, a1); red_pkt(oacc + 4 * LSTRIDE, b0, b1); }
    }

    const int pk = 32 * warp + 4 * g + 2 * (z & 1) + (z >> 1);
    {
        const float4* oacc = g_s.o_acc + (8 * h + (lane >> 3)) * LSTRIDE + (lane & 7);
        const uint32_t ob = sb + OFF_OB + 16 * lane;
        float4* hdst = g_s.h_acc[(lane >> 3) % HREP] + (10 * s + warp) * LSTRIDE + 4 * (g & 1) + 2 * (z & 1) + (z >> 1);
        pin64(hdst);
        unsigned it = 0;
        const uint32_t wa = sb + OFF_WO + (warp >= 5 ? 20480 + (warp - 5) * 32 : warp * 32) + (4 * (g >> 1) + z) * 160 + (g & 1) * 16;
        auto load_wo = [&]() {
            #pragma unroll
            for (int j = 0; j < 2; j++) {
                if (real) mbar_wait(BAR_WO + 16 * j + (warp >= 5 ? 8 : 0), 0);
                #pragma unroll
                for (int t = 4 * j; t < 4 * j + 4; t++) wr[t] = lds128(wa + t * 2560);
            }
        };
        if (warp == 8) {
            bool da = false, db = false;
            while (true) {
                #pragma unroll
                for (int j = 0; j < 3; j++) {
                    const uint32_t a = ob + 1024 * j;
                    const float c0 = ldsf(a + 8), c1 = ldsf(a + 512 + 8);
                    if (!da) {
                        if (c0 == 4.0f) { const float2 ev = lds64f(a); sts32(sb + OFF_OF + 4 * lane, pack_bf16(ev.x, ev.y)); da = true; }
                        else if (c0 >= 0.f) poll_async(a, oacc);
                    }
                    if (!db) {
                        if (c1 == 4.0f) { const float2 ev = lds64f(a + 512); sts32(sb + OFF_OF + 128 + 4 * lane, pack_bf16(ev.x, ev.y)); db = true; }
                        else if (c1 >= 0.f) poll_async(a + 512, oacc + 4 * LSTRIDE);
                    }
                    if (it == 0) __nanosleep(80);
                }
                if (__all_sync(0xffffffffu, da && db)) break;
                if (++it > 64u * SPIN_LIMIT) __trap();
            }
            __syncwarp();
            if (lane == 0) mbar_arrive(BAR_O);
        }
        load_wo();
        if (real) mbar_wait(BAR_O, 0);
        uint32_t op[8];
        #pragma unroll
        for (int t = 0; t < 8; t++) op[t] = lds32(sb + OFF_OF + 4 * (8 * t + 4 * (lane >> 4) + z));
        float c[4][4] = {};
        #pragma unroll
        for (int t = 0; t < 8; t++) {
            gemv_mma(c[t & 1], wr[t], op[t], selL0, selL1);
            gemv_mma(c[2 + (t & 1)], wr[t], op[t], selH0, selH1);
        }
        float v[4];
        #pragma unroll
        for (int k = 0; k < 4; k++) v[k] = (lane & 16) ? (c[2][k] + c[3][k]) : (c[0][k] + c[1][k]);
        const bool own = ((z >> 1) == ((g >> 1) & 1));
        const float sa = __shfl_xor_sync(0xffffffffu, (z & 2) ? v[0] : v[2], 2);
        const float sc = __shfl_xor_sync(0xffffffffu, (z & 2) ? v[1] : v[3], 2);
        float ra = own ? ((z & 2) ? v[2] : v[0]) : sa, rb = own ? ((z & 2) ? v[3] : v[1]) : sc;
        ra += __shfl_xor_sync(0xffffffffu, ra, 8);  rb += __shfl_xor_sync(0xffffffffu, rb, 8);
        ra += __shfl_xor_sync(0xffffffffu, ra, 16); rb += __shfl_xor_sync(0xffffffffu, rb, 16);
        if (real && lane < 8 * HREP) red_pkt(hdst, ra, rb);
    }

    if (bid < NFFN) {
        uint32_t bar_id = real ? 2 : 3, bar_n = real ? NTAIL : 32;
        const bool valid = ((z >> 1) == (lane >> 4));
        uint32_t pdst = sb + 4 * ((((g >> 1) & 1) * 16 + (g & 1) * 8 + (z & 1) * 4 + 2 * (lane >> 4)) * 12 + warp);
        uint32_t pdst2 = pdst + (real ? OFF_PART : OFF_CS);
        uint32_t psrc = sb + 48 * lane;
        const int p0 = 4 * (lane >> 4) + z;
        const int esw = z >> 1;
        const uint32_t xw = lds32(sb + OFF_X + 4 * (32 * warp + lane));
        const uint32_t wga = sb + OFF_GU + ((g >> 1) & 1) * 20480 + (64 * warp + 2 * p0) * 32 + (g & 1) * 16;
        uint32_t wda = sb + OFF_WD + z * WPITCH + warp * 128 + g * 16;
        const float4* hacc = g_s.h_acc[bid % HREP] + pk_idx(32 * warp + lane);
        const uint32_t hbuf = sb + OFF_HB + warp * 1024;
        float4* odst = g_s.out_acc + pk_idx(pk);
        uint32_t* outp = reinterpret_cast<uint32_t*>(out) + pk;
        uint32_t sf0 = esw ? selH0 : selL0, sf1 = esw ? selH1 : selL1;
        uint32_t ss0 = esw ? selL0 : selH0, ss1 = esw ? selL1 : selH1;
        pin32(bar_id); pin32(bar_n); pin32(pdst); pin32(pdst2); pin32(psrc); pin32(wda);
        pin32(sf0); pin32(sf1); pin32(ss0); pin32(ss1); pin64(odst); pin64(outp);
        uint4 wd4[4];
        unsigned it = 0;
        bool have_d = false;
        auto load_dn = [&]() {
            #pragma unroll
            for (int t = 0; t < 4; t++) wd4[t] = lds128(wda + 4 * t * WPITCH);
            have_d = true;
        };
        auto put_cols = [&](uint32_t dst, const float (&c)[4][4]) {
            float v[4];
            #pragma unroll
            for (int k = 0; k < 4; k++) v[k] = (c[0][k] + c[1][k]) + (c[2][k] + c[3][k]);
            const bool up = lane >= 16;
            const float r0 = __shfl_xor_sync(0xffffffffu, up ? v[0] : v[2], 18), r1 = __shfl_xor_sync(0xffffffffu, up ? v[1] : v[3], 18);
            if (valid) { stsf(dst, (up ? v[2] : v[0]) + r0); stsf(dst + 48, (up ? v[3] : v[1]) + r1); }
        };
        const uint32_t hmine = hbuf + 16 * lane;
        if (real) {
            mbar_wait(BAR_GU + 8, 0);
            poll_async(hmine, hacc);
            mbar_wait(BAR_GU, 0);
            if (warp >= 5) mbar_wait(BAR_GU + 16, 0);
            if (warp >= 7) { mbar_wait(BAR_GU + 24, 0); poll_async(hmine + 512, hacc); }
        }
        #pragma unroll
        for (int i = 0; i < 8; i++) wr[i] = lds128(wga + (16 * (i >> 1) + ((i & 1) ^ esw)) * 32);
        {
            float c[4][4] = {};
            #pragma unroll
            for (int i = 0; i < 8; i++) gemv_mma(c[i & 3], wr[i], 0x3f80u, selL0, selL1);
            put_cols(pdst + OFF_CS, c);
        }
        if (real && warp < 7) { mbar_wait(BAR_GU + 24, 0); poll_async(hmine + 512, hacc); }
        uint32_t hown = 0;
        {
            bool done = !real;
            while (true) {
                #pragma unroll
                for (int j = 0; j < 2; j++) {
                    const float4 ev = lds128f(hmine + 512 * j);
                    if (!done) {
                        if (ev.z == 32.0f) {
                            const uint32_t ab = pack_bf16(ev.x, ev.y);
                            hown = pack_bf16(bf_lo(xw) + bf_lo(ab), bf_hi(xw) + bf_hi(ab));
                            done = true;
                        } else if (ev.z >= 0.f) poll_async(hmine + 512 * j, hacc);
                    }
                }
                if (__all_sync(0xffffffffu, done)) break;
                if (!have_d && mbar_test(BAR_DN + 8, 0) && mbar_test(BAR_DN, 0)) load_dn();
                if (++it > 64u * SPIN_LIMIT) __trap();
            }
        }
        float c[4][4] = {};
        #pragma unroll
        for (int u = 0; u < 4; u++) {
            const uint32_t hb = __shfl_sync(0xffffffffu, hown, 8 * u + p0);
            gemv_mma(c[2 * (u & 1)], wr[2 * u], hb, sf0, sf1);
            gemv_mma(c[2 * (u & 1) + 1], wr[2 * u + 1], hb, ss0, ss1);
        }
        float s1 = bf_lo(hown) + bf_hi(hown), s2 = bf_lo(hown) * bf_lo(hown) + bf_hi(hown) * bf_hi(hown);
        #pragma unroll
        for (int o = 16; o > 0; o >>= 1) { s1 += __shfl_xor_sync(0xffffffffu, s1, o); s2 += __shfl_xor_sync(0xffffffffu, s2, o); }
        const uint32_t hfin = __shfl_sync(0xffffffffu, hown, pk & 31);
        if (real && lane == 0) { stsf(sb + OFF_STAT + 8 * warp, s1); stsf(sb + OFF_STAT + 8 * warp + 4, s2); }
        put_cols(pdst2, c);
        named_bar(bar_id, bar_n);
        float4 w[5];
        #pragma unroll
        for (int k = 0; k < 5; k++) w[k] = lds128f(sb + OFF_STAT + 16 * k);
        const float4 ga = lds128f(psrc + OFF_PART), gb = lds128f(psrc + OFF_PART + 16), ca = lds128f(psrc + OFF_CS), cb = lds128f(psrc + OFF_CS + 16);
        const float2 gc = lds64f(psrc + OFF_PART + 32), cc = lds64f(psrc + OFF_CS + 32);
        const float t1 = ((w[0].x + w[0].z) + (w[1].x + w[1].z)) + ((w[2].x + w[2].z) + (w[3].x + w[3].z)) + (w[4].x + w[4].z);
        const float t2 = ((w[0].y + w[0].w) + (w[1].y + w[1].w)) + ((w[2].y + w[2].w) + (w[3].y + w[3].w)) + (w[4].y + w[4].w);
        const float gs = (((ga.x + ga.y) + (ga.z + ga.w)) + ((gb.x + gb.y) + (gb.z + gb.w))) + (gc.x + gc.y);
        const float cs = (((ca.x + ca.y) + (ca.z + ca.w)) + ((cb.x + cb.y) + (cb.z + cb.w))) + (cc.x + cc.y);
        const float mean = t1 * (1.0f / D_MODEL);
        const float var = fmaxf(fmaf(t2, 1.0f / D_MODEL, -mean * mean), 0.f);
        const float den = bf16r(sqrt_fast(bf16r(bf16r(var) + 1e-5f)));
        const float val = bf16r(fmaf(-bf16r(mean), cs, gs) * rcp(den));
        const float oth = __shfl_xor_sync(0xffffffffu, val, 16);
        const float gv = (lane < 16) ? val : oth, uv = (lane < 16) ? oth : val;
        const float ey = ex2(gv * fmaf(gv * gv, -2.0f * LOG2E * 0.7978845608028654f * 0.044715f, -2.0f * LOG2E * 0.7978845608028654f));
        const uint32_t hh = pack_bf16(bf16r(gv * rcp(1.0f + ey)) * uv, 0.f);
        if (!have_d) {
            if (real) { mbar_wait(BAR_DN, 0); mbar_wait(BAR_DN + 8, 0); }
            load_dn();
        }
        float d[4][4] = {};
        #pragma unroll
        for (int t = 0; t < 4; t++) gemv_mma(d[t], wd4[t], __shfl_sync(0xffffffffu, hh, 4 * t + z), selL0, selL1);
        const float ra = (z & 2) ? ((d[0][2] + d[1][2]) + (d[2][2] + d[3][2])) : ((d[0][0] + d[1][0]) + (d[2][0] + d[3][0]));
        const float rb = (z & 2) ? ((d[0][3] + d[1][3]) + (d[2][3] + d[3][3])) : ((d[0][1] + d[1][1]) + (d[2][1] + d[3][1]));
        if (real) {
            float4 old;
            asm volatile("atom.relaxed.gpu.global.add.v4.f32 {%0,%1,%2,%3}, [%4], {%5,%6,%7,%8};"
                         : "=f"(old.x), "=f"(old.y), "=f"(old.z), "=f"(old.w)
                         : "l"(odst), "f"(ra), "f"(rb), "f"(1.0f), "f"(0.0f) : "memory");
            if (old.z == (float)(NFFN - 1)) {
                const uint32_t fb = pack_bf16(old.x + ra, old.y + rb);
                *outp = pack_bf16(bf_lo(hfin) + bf_lo(fb), bf_hi(hfin) + bf_hi(fb));
                if (pk == 0) g_epoch = (tag >= 0xfffffffeu) ? 1u : tag + 1u;
            }
        }
    }
    }
    asm volatile("cp.async.wait_all;" ::: "memory");
}

__device__ float g_fq[NH * DH], g_fo[NH * DH], g_fh[D_MODEL], g_fa[DFF];
__device__ __forceinline__ float bf2f(__nv_bfloat16 v) { return __bfloat162float(v); }
__device__ float block_reduce(float v, bool is_max, float* red) {
    for (int o = 16; o > 0; o >>= 1) { const float w = __shfl_xor_sync(0xffffffffu, v, o); v = is_max ? fmaxf(v, w) : v + w; }
    __syncthreads();
    if ((threadIdx.x & 31) == 0) red[threadIdx.x >> 5] = v;
    __syncthreads();
    v = red[0];
    for (int i = 1; i < (int)(blockDim.x >> 5); i++) v = is_max ? fmaxf(v, red[i]) : v + red[i];
    return v;
}
__device__ void block_layernorm(const __nv_bfloat16* xb, const float* xf, float* dst, float* red) {
    float sum = 0.f;
    for (int i = threadIdx.x; i < D_MODEL; i += blockDim.x) { dst[i] = xb ? bf2f(xb[i]) : xf[i]; sum += dst[i]; }
    const float mean = block_reduce(sum, false, red) * (1.0f / D_MODEL);
    float sq = 0.f;
    for (int i = threadIdx.x; i < D_MODEL; i += blockDim.x) sq += (dst[i] - mean) * (dst[i] - mean);
    const float den = bf16r(sqrtf(bf16r(bf16r(block_reduce(sq, false, red) * (1.0f / D_MODEL)) + 1e-5f)));
    for (int i = threadIdx.x; i < D_MODEL; i += blockDim.x) dst[i] = bf16r(bf16r(dst[i] - bf16r(mean)) / den);
    __syncthreads();
}
__global__ void fb_q(const __nv_bfloat16* x, const __nv_bfloat16* wq) {
    __shared__ float xn[D_MODEL], red[8];
    block_layernorm(x, nullptr, xn, red);
    const int c = blockIdx.x * 128 + threadIdx.x;
    float a = 0.f;
    for (int r = 0; r < D_MODEL; r++) a += xn[r] * bf2f(wq[(size_t)r * (NH * DH) + c]);
    g_fq[c] = bf16r(a);
}
__global__ void fb_attn(const __nv_bfloat16* kc, const __nv_bfloat16* vc) {
    __shared__ float sc[SK], red[8];
    const int h = blockIdx.x;
    float m = -INFINITY;
    for (int j = threadIdx.x; j < SK; j += 128) {
        float a = 0.f;
        for (int d = 0; d < DH; d++) a += g_fq[h * DH + d] * bf2f(kc[((size_t)h * SK + j) * DH + d]);
        sc[j] = bf16r(bf16r(a) * 0.08838834764831845f);
        m = fmaxf(m, sc[j]);
    }
    m = block_reduce(m, true, red);
    float l = 0.f;
    for (int j = threadIdx.x; j < SK; j += 128) { sc[j] = expf(sc[j] - m); l += sc[j]; }
    l = block_reduce(l, false, red);
    __syncthreads();
    float a = 0.f;
    for (int j = 0; j < SK; j++) a += bf16r(sc[j] / l) * bf2f(vc[((size_t)h * SK + j) * DH + threadIdx.x]);
    g_fo[h * DH + threadIdx.x] = bf16r(a);
}
__global__ void fb_h(const __nv_bfloat16* x, const __nv_bfloat16* wo) {
    const int c = blockIdx.x * 128 + threadIdx.x;
    float a = 0.f;
    for (int r = 0; r < NH * DH; r++) a += g_fo[r] * bf2f(wo[(size_t)r * D_MODEL + c]);
    g_fh[c] = bf16r(bf2f(x[c]) + bf16r(a));
}
__global__ void fb_act(const __nv_bfloat16* wg, const __nv_bfloat16* wu) {
    __shared__ float hn[D_MODEL], red[8];
    block_layernorm(nullptr, g_fh, hn, red);
    const int c = blockIdx.x * 64 + threadIdx.x;
    float a = 0.f, b = 0.f;
    for (int r = 0; r < D_MODEL; r++) { a += hn[r] * bf2f(wg[(size_t)r * DFF + c]); b += hn[r] * bf2f(wu[(size_t)r * DFF + c]); }
    const float gv = bf16r(a);
    g_fa[c] = bf16r(bf16r(0.5f * gv * (1.0f + tanhf(0.7978845608028654f * (gv + 0.044715f * gv * gv * gv)))) * bf16r(b));
}
__global__ void fb_out(const __nv_bfloat16* wd, __nv_bfloat16* out) {
    const int c = blockIdx.x * 128 + threadIdx.x;
    float a = 0.f;
    for (int r = 0; r < DFF; r++) a += g_fa[r] * bf2f(wd[(size_t)r * D_MODEL + c]);
    out[c] = __float2bfloat16_rn(g_fh[c] + bf16r(a));
}

typedef CUresult (*EncodeFn)(CUtensorMap*, CUtensorMapDataType, cuuint32_t, void*, const cuuint64_t*, const cuuint64_t*,
                             const cuuint32_t*, const cuuint32_t*, CUtensorMapInterleave, CUtensorMapSwizzle,
                             CUtensorMapL2promotion, CUtensorMapFloatOOBfill);

void make_map(EncodeFn fn, CUtensorMap* m, void* base, int rows, int cols, int box_cols, int box_rows,
              CUtensorMapL2promotion promo) {
    cuuint64_t dims[2] = {(cuuint64_t)cols, (cuuint64_t)rows};
    cuuint64_t strides[1] = {(cuuint64_t)cols * 2};
    cuuint32_t box[2] = {(cuuint32_t)box_cols, (cuuint32_t)box_rows};
    cuuint32_t es[2] = {1, 1};
    fn(m, CU_TENSOR_MAP_DATA_TYPE_BFLOAT16, 2, base, dims, strides, box, es, CU_TENSOR_MAP_INTERLEAVE_NONE,
       CU_TENSOR_MAP_SWIZZLE_NONE, promo, CU_TENSOR_MAP_FLOAT_OOB_FILL_NONE);
}

}

extern "C" void kernel_launch(void* const* d_in, const int* in_sizes, int n_in, void* d_out, int out_size) {
    (void)in_sizes; (void)n_in; (void)out_size;
    typedef const __nv_bfloat16* cbf;
    static int mode = -1;
    static EncodeFn encode = nullptr;
    if (mode < 0) {
        void* fn = nullptr;
        cudaDriverEntryPointQueryResult st;
        int dev = 0, sms = 0, occ = 0;
        bool ok = cudaGetDriverEntryPoint("cuTensorMapEncodeTiled", &fn, cudaEnableDefault, &st) == cudaSuccess && fn != nullptr;
        ok = ok && cudaFuncSetAttribute(fused_decode_kernel, cudaFuncAttributeMaxDynamicSharedMemorySize, SMEM_BYTES) == cudaSuccess;
        ok = ok && cudaGetDevice(&dev) == cudaSuccess && cudaDeviceGetAttribute(&sms, cudaDevAttrMultiProcessorCount, dev) == cudaSuccess;
        ok = ok && cudaOccupancyMaxActiveBlocksPerMultiprocessor(&occ, fused_decode_kernel, NTHREADS, SMEM_BYTES) == cudaSuccess;
        encode = (EncodeFn)fn;
        mode = (ok && sms * occ >= NCTA) ? 1 : 0;
    }
    if (mode == 0) {
        fb_q<<<NH, 128>>>((cbf)d_in[0], (cbf)d_in[3]);
        fb_attn<<<NH, 128>>>((cbf)d_in[1], (cbf)d_in[2]);
        fb_h<<<D_MODEL / 128, 128>>>((cbf)d_in[0], (cbf)d_in[4]);
        fb_act<<<DFF / 64, 64>>>((cbf)d_in[6], (cbf)d_in[7]);
        fb_out<<<D_MODEL / 128, 128>>>((cbf)d_in[8], (__nv_bfloat16*)d_out);
        return;
    }
    CUtensorMap mq, mg, mu, mo;
    make_map(encode, &mq, d_in[3], D_MODEL, NH * DH, 32, 160, CU_TENSOR_MAP_L2_PROMOTION_NONE);
    make_map(encode, &mg, d_in[6], D_MODEL, DFF, 16, 160, CU_TENSOR_MAP_L2_PROMOTION_L2_128B);
    make_map(encode, &mu, d_in[7], D_MODEL, DFF, 16, 160, CU_TENSOR_MAP_L2_PROMOTION_L2_128B);
    make_map(encode, &mo, d_in[4], NH * DH, D_MODEL, 80, 64, CU_TENSOR_MAP_L2_PROMOTION_L2_256B);
    fused_decode_kernel<<<NCTA, NTHREADS, SMEM_BYTES>>>(mq, mg, mu, mo, (cbf)d_in[0], (cbf)d_in[1], (cbf)d_in[2],
                                                        (cbf)d_in[8], (__nv_bfloat16*)d_out);
}
```
